```python
import torch

def _softmax(x, axis=-1):
    return torch.softmax(x, dim=axis)
def _gelu(x):
    return torch.nn.functional.gelu(x, approximate="tanh")
def _silu(x):
    return torch.nn.functional.silu(x)
def _sigmoid(x):
    return torch.sigmoid(x)
def _layernorm(x, axis=-1, eps=1e-5):
    m = x.mean(dim=axis, keepdim=True)
    v = x.var(dim=axis, keepdim=True, unbiased=False)
    return (x - m) / torch.sqrt(v + eps)
def _scatter_add(tgt, idx, src, axis=0):
    return tgt.clone().index_add_(axis, idx, src)
def _segment_sum(src, seg, n):
    out = torch.zeros((n,) + src.shape[1:], dtype=src.dtype)
    return out.index_add_(0, seg, src)
def _pad(x, pw):
    flat = tuple(v for pair in reversed(pw) for v in pair)
    return torch.nn.functional.pad(x, flat)

kernel_name = 'recurrent_scan__mha_block_cached__mixer_channel_mlp__prompt'

def setup_inputs():

    _w = (lambda a: (lambda t: t.to(torch.bfloat16) if t.is_floating_point() else t)(torch.as_tensor(a)))
    def _A_setup():
        B, Sq, D = 1, 2048, 512
        H, Sk, Dh = 32, 2048, 128
        return {
            "x": _w((lambda *s: torch.randn(*s, dtype=torch.bfloat16) * 0.05)(B, Sq, D)),
            "k_cache": _w((lambda *s: torch.randn(*s, dtype=torch.bfloat16) * 1.6)(B, H, Sk, Dh)),
            "v_cache": _w((lambda *s: torch.randn(*s, dtype=torch.bfloat16) * 0.8)(B, H, Sk, Dh)),
            "wq": _w((lambda *s: torch.randn(*s, dtype=torch.bfloat16) * 1.6)(D, H * Dh) * (D ** -0.5)),
            "wo": _w((lambda *s: torch.randn(*s, dtype=torch.bfloat16) * 0.8)(H * Dh, D) * ((H * Dh) ** -0.5)),
        }
    _A_in = _A_setup()

    def _B_setup():
        B, S, D, F = 1, 2048, 512, 1376
        return {
            "x": _w((lambda *s: torch.randn(*s, dtype=torch.bfloat16) * 0.05)(B, S, D)),
            "w1": _w((lambda *s: torch.randn(*s, dtype=torch.bfloat16) * 1.6)(D, F) * (D ** -0.5)),
            "b1": _w((lambda *s: torch.randn(*s, dtype=torch.bfloat16) * 0.8)(F)),
            "w2": _w((lambda *s: torch.randn(*s, dtype=torch.bfloat16) * 0.2)(F, D) * (F ** -0.5)),
            "b2": _w((lambda *s: torch.randn(*s, dtype=torch.bfloat16) * 0.2)(D)),
        }
    _B_in = _B_setup()

    return {
        "A_x": _A_in["x"],
        "A_k_cache": _A_in["k_cache"],
        "A_v_cache": _A_in["v_cache"],
        "A_wq": _A_in["wq"],
        "A_wo": _A_in["wo"],
        "B_x": _B_in["x"],
        "B_w1": _B_in["w1"],
        "B_b1": _B_in["b1"],
        "B_w2": _B_in["w2"],
        "B_b2": _B_in["b2"],
    }

def reference(A_x, A_k_cache, A_v_cache, A_wq, A_wo, B_x, B_w1, B_b1, B_w2, B_b2):
    def _A_ref(x, k_cache, v_cache, wq, wo):
        B, Sq, D = x.shape
        H, Dh = 32, 128
        q = (lambda x, *d: x.permute(*d))((x @ wq).reshape(B, Sq, H, Dh), 0, 2, 1, 3)
        scores = torch.einsum("bhqd,bhkd->bhqk", q, k_cache) * (Dh ** -0.5)
        p = _softmax(scores, axis=-1)
        o = torch.einsum("bhqk,bhkd->bhqd", p, v_cache)
        return (lambda x, *d: x.permute(*d))(o, 0, 2, 1, 3).reshape(B, Sq, H * Dh) @ wo

    def _B_ref(x, w1, b1, w2, b2):
        y = _layernorm(x, axis=-1)
        h = _gelu(torch.einsum("bsd,df->bsf", y, w1) + b1)
        return torch.einsum("bsf,fd->bsd", h, w2) + b2

    x = A_x
    xn = _layernorm(x, axis=-1)
    s = _A_ref(xn, A_k_cache, A_v_cache, A_wq, A_wo)
    g = _silu(_B_ref(xn, B_w1, B_b1, B_w2, B_b2))
    return x + s * g
```

```cpp
#include <cuda_runtime.h>
#include <cuda_bf16.h>
#include <cuda.h>
#include <stdint.h>

typedef __nv_bfloat16 bf16;

constexpr int SQ = 2048, DM = 512, NH = 32, DH = 128, FF = 1376, HD = 4096;

__device__ __align__(1024) bf16 g_xn[SQ * DM];
__device__ __align__(1024) bf16 g_y[SQ * DM];
__device__ __align__(1024) bf16 g_o[SQ * HD];
__device__ __align__(1024) bf16 g_h[SQ * FF];

__device__ __forceinline__ uint32_t smem_u32(const void* p) { return (uint32_t)__cvta_generic_to_shared(p); }
__device__ __forceinline__ void mbar_init(uint32_t bar, uint32_t count) {
  asm volatile("mbarrier.init.shared::cta.b64 [%0], %1;" ::"r"(bar), "r"(count));
}
__device__ __forceinline__ void mbar_expect_tx(uint32_t bar, uint32_t bytes) {
  asm volatile("mbarrier.arrive.expect_tx.shared::cta.b64 _, [%0], %1;" ::"r"(bar), "r"(bytes) : "memory");
}
__device__ __forceinline__ void mbar_arrive(uint32_t bar) {
  asm volatile("mbarrier.arrive.shared::cta.b64 _, [%0];" ::"r"(bar) : "memory");
}
__device__ __forceinline__ void mbar_wait(uint32_t bar, uint32_t parity) {
  asm volatile(
      "{\n.reg .pred P1;\n"
      "LAB_WAIT:\n"
      "mbarrier.try_wait.parity.shared::cta.b64 P1, [%0], %1;\n"
      "@P1 bra DONE;\n"
      "bra LAB_WAIT;\n"
      "DONE:\n}\n" ::"r"(bar), "r"(parity) : "memory");
}
__device__ __forceinline__ void tma_load_2d(uint32_t dst, const CUtensorMap* tm, uint32_t bar, int c0, int c1) {
  asm volatile(
      "cp.async.bulk.tensor.2d.shared::cluster.global.mbarrier::complete_tx::bytes [%0], [%1, {%3, %4}], [%2];"
      ::"r"(dst), "l"((uint64_t)tm), "r"(bar), "r"(c0), "r"(c1) : "memory");
}
__device__ __forceinline__ void tma_store_2d(const CUtensorMap* tm, uint32_t src, int c0, int c1) {
  asm volatile("cp.async.bulk.tensor.2d.global.shared::cta.bulk_group [%0, {%2, %3}], [%1];"
               ::"l"((uint64_t)tm), "r"(src), "r"(c0), "r"(c1) : "memory");
}
__device__ __forceinline__ void tma_store_commit() { asm volatile("cp.async.bulk.commit_group;" ::: "memory"); }
__device__ __forceinline__ void tma_store_wait_read() { asm volatile("cp.async.bulk.wait_group.read 0;" ::: "memory"); }
__device__ __forceinline__ void fence_proxy_async() { asm volatile("fence.proxy.async.shared::cta;" ::: "memory"); }
__device__ __forceinline__ void named_bar_sync(int id, int n) { asm volatile("bar.sync %0, %1;" ::"r"(id), "r"(n) : "memory"); }
__device__ __forceinline__ void named_bar_arrive(int id, int n) { asm volatile("bar.arrive %0, %1;" ::"r"(id), "r"(n) : "memory"); }
__device__ __forceinline__ void wgmma_fence() { asm volatile("wgmma.fence.sync.aligned;" ::: "memory"); }
__device__ __forceinline__ void wgmma_commit() { asm volatile("wgmma.commit_group.sync.aligned;" ::: "memory"); }
template <int N> __device__ __forceinline__ void wgmma_wait() { asm volatile("wgmma.wait_group.sync.aligned %0;" ::"n"(N) : "memory"); }
template <int R> __device__ __forceinline__ void reg_alloc() { asm volatile("setmaxnreg.inc.sync.aligned.u32 %0;" ::"n"(R)); }
template <int R> __device__ __forceinline__ void reg_dealloc() { asm volatile("setmaxnreg.dec.sync.aligned.u32 %0;" ::"n"(R)); }

__device__ __forceinline__ uint64_t make_desc(uint32_t addr, uint32_t lbo_bytes, uint32_t sbo_bytes) {
  return (uint64_t)((addr & 0x3FFFF) >> 4) | ((uint64_t)(lbo_bytes >> 4) << 16) | ((uint64_t)(sbo_bytes >> 4) << 32) |
         ((uint64_t)1 << 62);
}
__device__ __forceinline__ uint32_t pack_bf16(float lo, float hi) {
  uint32_t r;
  asm("cvt.rn.bf16x2.f32 %0, %1, %2;" : "=r"(r) : "f"(hi), "f"(lo));
  return r;
}
__device__ __forceinline__ float ex2(float x) {
  float y;
  asm("ex2.approx.ftz.f32 %0, %1;" : "=f"(y) : "f"(x));
  return y;
}

template<int TB> __device__ __forceinline__ void wgmma_m64n64k16_ss(float (&d)[32], uint64_t da, uint64_t db, int scaleD) {
  asm volatile("{\n.reg .pred p;\nsetp.ne.b32 p, %34, 0;\n"
    "wgmma.mma_async.sync.aligned.m64n64k16.f32.bf16.bf16 {%0, %1, %2, %3, %4, %5, %6, %7, %8, %9, %10, %11, %12, %13, %14, %15, %16, %17, %18, %19, %20, %21, %22, %23, %24, %25, %26, %27, %28, %29, %30, %31}, %32, %33, p, 1, 1, 0, %35;\n}\n"
    : "+f"(d[0]), "+f"(d[1]), "+f"(d[2]), "+f"(d[3]), "+f"(d[4]), "+f"(d[5]), "+f"(d[6]), "+f"(d[7]), "+f"(d[8]), "+f"(d[9]), "+f"(d[10]), "+f"(d[11]), "+f"(d[12]), "+f"(d[13]), "+f"(d[14]), "+f"(d[15]), "+f"(d[16]), "+f"(d[17]), "+f"(d[18]), "+f"(d[19]), "+f"(d[20]), "+f"(d[21]), "+f"(d[22]), "+f"(d[23]), "+f"(d[24]), "+f"(d[25]), "+f"(d[26]), "+f"(d[27]), "+f"(d[28]), "+f"(d[29]), "+f"(d[30]), "+f"(d[31])
    : "l"(da), "l"(db), "r"(scaleD), "n"(TB));
}
template<int TB> __device__ __forceinline__ void wgmma_m64n128k16_ss(float (&d)[64], uint64_t da, uint64_t db, int scaleD) {
  asm volatile("{\n.reg .pred p;\nsetp.ne.b32 p, %66, 0;\n"
    "wgmma.mma_async.sync.aligned.m64n128k16.f32.bf16.bf16 {%0, %1, %2, %3, %4, %5, %6, %7, %8, %9, %10, %11, %12, %13, %14, %15, %16, %17, %18, %19, %20, %21, %22, %23, %24, %25, %26, %27, %28, %29, %30, %31, %32, %33, %34, %35, %36, %37, %38, %39, %40, %41, %42, %43, %44, %45, %46, %47, %48, %49, %50, %51, %52, %53, %54, %55, %56, %57, %58, %59, %60, %61, %62, %63}, %64, %65, p, 1, 1, 0, %67;\n}\n"
    : "+f"(d[0]), "+f"(d[1]), "+f"(d[2]), "+f"(d[3]), "+f"(d[4]), "+f"(d[5]), "+f"(d[6]), "+f"(d[7]), "+f"(d[8]), "+f"(d[9]), "+f"(d[10]), "+f"(d[11]), "+f"(d[12]), "+f"(d[13]), "+f"(d[14]), "+f"(d[15]), "+f"(d[16]), "+f"(d[17]), "+f"(d[18]), "+f"(d[19]), "+f"(d[20]), "+f"(d[21]), "+f"(d[22]), "+f"(d[23]), "+f"(d[24]), "+f"(d[25]), "+f"(d[26]), "+f"(d[27]), "+f"(d[28]), "+f"(d[29]), "+f"(d[30]), "+f"(d[31]), "+f"(d[32]), "+f"(d[33]), "+f"(d[34]), "+f"(d[35]), "+f"(d[36]), "+f"(d[37]), "+f"(d[38]), "+f"(d[39]), "+f"(d[40]), "+f"(d[41]), "+f"(d[42]), "+f"(d[43]), "+f"(d[44]), "+f"(d[45]), "+f"(d[46]), "+f"(d[47]), "+f"(d[48]), "+f"(d[49]), "+f"(d[50]), "+f"(d[51]), "+f"(d[52]), "+f"(d[53]), "+f"(d[54]), "+f"(d[55]), "+f"(d[56]), "+f"(d[57]), "+f"(d[58]), "+f"(d[59]), "+f"(d[60]), "+f"(d[61]), "+f"(d[62]), "+f"(d[63])
    : "l"(da), "l"(db), "r"(scaleD), "n"(TB));
}
template<int TB> __device__ __forceinline__ void wgmma_m64n128k16_rs(float (&d)[64], uint32_t a0, uint32_t a1, uint32_t a2, uint32_t a3, uint64_t db, int scaleD) {
  asm volatile("{\n.reg .pred p;\nsetp.ne.b32 p, %69, 0;\n"
    "wgmma.mma_async.sync.aligned.m64n128k16.f32.bf16.bf16 {%0, %1, %2, %3, %4, %5, %6, %7, %8, %9, %10, %11, %12, %13, %14, %15, %16, %17, %18, %19, %20, %21, %22, %23, %24, %25, %26, %27, %28, %29, %30, %31, %32, %33, %34, %35, %36, %37, %38, %39, %40, %41, %42, %43, %44, %45, %46, %47, %48, %49, %50, %51, %52, %53, %54, %55, %56, %57, %58, %59, %60, %61, %62, %63}, {%64, %65, %66, %67}, %68, p, 1, 1, %70;\n}\n"
    : "+f"(d[0]), "+f"(d[1]), "+f"(d[2]), "+f"(d[3]), "+f"(d[4]), "+f"(d[5]), "+f"(d[6]), "+f"(d[7]), "+f"(d[8]), "+f"(d[9]), "+f"(d[10]), "+f"(d[11]), "+f"(d[12]), "+f"(d[13]), "+f"(d[14]), "+f"(d[15]), "+f"(d[16]), "+f"(d[17]), "+f"(d[18]), "+f"(d[19]), "+f"(d[20]), "+f"(d[21]), "+f"(d[22]), "+f"(d[23]), "+f"(d[24]), "+f"(d[25]), "+f"(d[26]), "+f"(d[27]), "+f"(d[28]), "+f"(d[29]), "+f"(d[30]), "+f"(d[31]), "+f"(d[32]), "+f"(d[33]), "+f"(d[34]), "+f"(d[35]), "+f"(d[36]), "+f"(d[37]), "+f"(d[38]), "+f"(d[39]), "+f"(d[40]), "+f"(d[41]), "+f"(d[42]), "+f"(d[43]), "+f"(d[44]), "+f"(d[45]), "+f"(d[46]), "+f"(d[47]), "+f"(d[48]), "+f"(d[49]), "+f"(d[50]), "+f"(d[51]), "+f"(d[52]), "+f"(d[53]), "+f"(d[54]), "+f"(d[55]), "+f"(d[56]), "+f"(d[57]), "+f"(d[58]), "+f"(d[59]), "+f"(d[60]), "+f"(d[61]), "+f"(d[62]), "+f"(d[63])
    : "r"(a0), "r"(a1), "r"(a2), "r"(a3), "l"(db), "r"(scaleD), "n"(TB));
}


__global__ void __launch_bounds__(256) ln_kernel(const bf16* __restrict__ x) {
  int row = blockIdx.x * 8 + (threadIdx.x >> 5);
  int lane = threadIdx.x & 31;
  const uint4* px = reinterpret_cast<const uint4*>(x + row * DM);
  float v[16];
#pragma unroll
  for (int i = 0; i < 2; i++) {
    uint4 u = px[lane + 32 * i];
    const uint32_t w[4] = {u.x, u.y, u.z, u.w};
#pragma unroll
    for (int j = 0; j < 4; j++) {
      v[i * 8 + j * 2] = __uint_as_float(w[j] << 16);
      v[i * 8 + j * 2 + 1] = __uint_as_float(w[j] & 0xffff0000u);
    }
  }
#pragma unroll
  for (int pass = 0; pass < 2; pass++) {
    float s = 0.f;
#pragma unroll
    for (int i = 0; i < 16; i++) s += v[i];
#pragma unroll
    for (int o = 16; o > 0; o >>= 1) s += __shfl_xor_sync(0xffffffffu, s, o);
    float m = s * (1.0f / DM);
    float q = 0.f;
#pragma unroll
    for (int i = 0; i < 16; i++) { float d = v[i] - m; q += d * d; }
#pragma unroll
    for (int o = 16; o > 0; o >>= 1) q += __shfl_xor_sync(0xffffffffu, q, o);
    float rs = rsqrtf(q * (1.0f / DM) + 1e-5f);
    uint32_t w[8];
#pragma unroll
    for (int i = 0; i < 8; i++) {
      float a = (v[2 * i] - m) * rs, b = (v[2 * i + 1] - m) * rs;
      w[i] = pack_bf16(a, b);
      v[2 * i] = __uint_as_float(w[i] << 16);
      v[2 * i + 1] = __uint_as_float(w[i] & 0xffff0000u);
    }
    uint4* pd = reinterpret_cast<uint4*>((pass == 0 ? g_xn : g_y) + row * DM);
    pd[lane] = make_uint4(w[0], w[1], w[2], w[3]);
    pd[lane + 32] = make_uint4(w[4], w[5], w[6], w[7]);
  }
}

constexpr int ATT_CTAS = NH * (SQ / 128);
constexpr int MLP1_NT = (FF + 127) / 128;
constexpr int MLP1_CTAS = (SQ / 128) * MLP1_NT;
constexpr int SM_Q = 0, SM_K = 32768, SM_V = 32768 + 65536, SM_BAR = 32768 + 131072;
constexpr int ATT_SMEM = SM_BAR + 128 + 1024;

__device__ __forceinline__ void store_acc_sw128(uint32_t sbase, int cw, const float (&acc)[64], float mul0, float mul1) {
  int t = threadIdx.x & 127;
  int warp = t >> 5, lane = t & 31;
  int r0 = cw * 64 + warp * 16 + (lane >> 2);
#pragma unroll
  for (int j = 0; j < 16; j++) {
    int col = j * 8 + (lane & 3) * 2;
    int chunk = col >> 6;
    int g = (col & 63) >> 3;
    uint32_t a0 = sbase + chunk * 16384 + r0 * 128 + ((g ^ (r0 & 7)) << 4) + (col & 7) * 2;
    uint32_t a1 = a0 + 8 * 128;
    uint32_t p0 = pack_bf16(acc[j * 4 + 0] * mul0, acc[j * 4 + 1] * mul0);
    uint32_t p1 = pack_bf16(acc[j * 4 + 2] * mul1, acc[j * 4 + 3] * mul1);
    asm volatile("st.shared.b32 [%0], %1;" ::"r"(a0), "r"(p0) : "memory");
    asm volatile("st.shared.b32 [%0], %1;" ::"r"(a1), "r"(p1) : "memory");
  }
}

__device__ __forceinline__ float gelu_tanh(float x) {
  const float k0 = 0.7978845608028654f, k1 = 0.044715f;
  float u = k0 * (x + k1 * x * x * x);
  float t = tanhf(u);
  return 0.5f * x * (1.0f + t);
}

__global__ void __launch_bounds__(384, 1)
attn_kernel(const __grid_constant__ CUtensorMap tm_xn, const __grid_constant__ CUtensorMap tm_y,
            const __grid_constant__ CUtensorMap tm_wq, const __grid_constant__ CUtensorMap tm_w1,
            const __grid_constant__ CUtensorMap tm_k, const __grid_constant__ CUtensorMap tm_v,
            const __grid_constant__ CUtensorMap tm_o, const __grid_constant__ CUtensorMap tm_h,
            const bf16* __restrict__ b1) {
  extern __shared__ uint8_t smem_raw[];
  uint32_t sb = (smem_u32(smem_raw) + 1023) & ~1023u;
  const uint32_t sQ = sb + SM_Q, sK = sb + SM_K, sV = sb + SM_V, sBar = sb + SM_BAR;
  auto fullK = [&](int s) { return sBar + 8 * s; };
  auto fullV = [&](int s) { return sBar + 16 + 8 * s; };
  auto emptyK = [&](int s) { return sBar + 32 + 8 * s; };
  auto emptyV = [&](int s) { return sBar + 48 + 8 * s; };

  const bool is_mlp = blockIdx.x >= ATT_CTAS;
  int head, mt, n0;
  if (!is_mlp) { head = blockIdx.x >> 4; mt = blockIdx.x & 15; n0 = head * 128; }
  else { int i = blockIdx.x - ATT_CTAS; mt = i & 15; head = 0; n0 = (i >> 4) * 128; }

  const int wg = threadIdx.x >> 7;
  if (threadIdx.x == 0) {
    for (int s = 0; s < 2; s++) {
      mbar_init(fullK(s), 1); mbar_init(fullV(s), 1);
      mbar_init(emptyK(s), 8); mbar_init(emptyV(s), 8);
    }
    asm volatile("fence.mbarrier_init.release.cluster;" ::: "memory");
  }
  __syncthreads();

  if (wg == 0) {
    reg_dealloc<24>();
    if (threadIdx.x == 0) {
      const CUtensorMap* ta = is_mlp ? &tm_y : &tm_xn;
      const CUtensorMap* tb = is_mlp ? &tm_w1 : &tm_wq;
      for (int c = 0; c < 8; c++) {
        int it = c >> 1, st = it & 1;
        uint32_t buf = ((c & 1) ? sV : sK) + st * 32768;
        uint32_t fb = (c & 1) ? fullV(st) : fullK(st);
        uint32_t eb = (c & 1) ? emptyV(st) : emptyK(st);
        mbar_wait(eb, ((it >> 1) & 1) ^ 1);
        mbar_expect_tx(fb, 32768);
        tma_load_2d(buf, ta, fb, c * 64, mt * 128);
        tma_load_2d(buf + 16384, tb, fb, n0, c * 64);
        tma_load_2d(buf + 24576, tb, fb, n0 + 64, c * 64);
      }
      if (!is_mlp) {
        for (int n = 0; n < 16; n++) {
          int it = 4 + n, st = it & 1;
          uint32_t ph = ((it >> 1) & 1) ^ 1;
          int row = head * SQ + n * 128;
          mbar_wait(emptyK(st), ph);
          mbar_expect_tx(fullK(st), 32768);
          tma_load_2d(sK + st * 32768, &tm_k, fullK(st), 0, row);
          tma_load_2d(sK + st * 32768 + 16384, &tm_k, fullK(st), 64, row);
          mbar_wait(emptyV(st), ph);
          mbar_expect_tx(fullV(st), 32768);
          tma_load_2d(sV + st * 32768, &tm_v, fullV(st), 0, row);
          tma_load_2d(sV + st * 32768 + 16384, &tm_v, fullV(st), 64, row);
        }
      }
    }
  } else {
    reg_alloc<240>();
    const int cw = wg - 1;
    const int lane = threadIdx.x & 31;
    float acc[64];
#pragma unroll
    for (int i = 0; i < 64; i++) acc[i] = 0.f;
    for (int c = 0; c < 8; c++) {
      int it = c >> 1, st = it & 1;
      uint32_t buf = ((c & 1) ? sV : sK) + st * 32768;
      uint32_t fb = (c & 1) ? fullV(st) : fullK(st);
      uint32_t eb = (c & 1) ? emptyV(st) : emptyK(st);
      mbar_wait(fb, (it >> 1) & 1);
      wgmma_fence();
#pragma unroll
      for (int kk = 0; kk < 4; kk++) {
        uint64_t da = make_desc(buf + cw * 8192 + kk * 32, 16, 1024);
        uint64_t db = make_desc(buf + 16384 + kk * 2048, 8192, 1024);
        wgmma_m64n128k16_ss<1>(acc, da, db, 1);
      }
      wgmma_commit();
      wgmma_wait<0>();
      if (lane == 0) mbar_arrive(eb);
    }
    if (is_mlp) {
      int t = threadIdx.x & 127;
      int cbase = n0 + (lane & 3) * 2;
#pragma unroll
      for (int j = 0; j < 16; j++) {
        int col = cbase + j * 8;
        float bb0 = 0.f, bb1 = 0.f;
        if (col < FF) { bb0 = __bfloat162float(b1[col]); bb1 = __bfloat162float(b1[col + 1]); }
        acc[j * 4 + 0] = gelu_tanh(acc[j * 4 + 0] + bb0);
        acc[j * 4 + 1] = gelu_tanh(acc[j * 4 + 1] + bb1);
        acc[j * 4 + 2] = gelu_tanh(acc[j * 4 + 2] + bb0);
        acc[j * 4 + 3] = gelu_tanh(acc[j * 4 + 3] + bb1);
      }
      store_acc_sw128(sQ, cw, acc, 1.f, 1.f);
      fence_proxy_async();
      named_bar_sync(1 + cw, 128);
      if (t == 0) {
        tma_store_2d(&tm_h, sQ + cw * 8192, n0, mt * 128 + cw * 64);
        if (n0 + 64 < FF) tma_store_2d(&tm_h, sQ + 16384 + cw * 8192, n0 + 64, mt * 128 + cw * 64);
        tma_store_commit();
        tma_store_wait_read();
      }
      return;
    }
    store_acc_sw128(sQ, cw, acc, 1.f, 1.f);
    fence_proxy_async();
    named_bar_sync(1 + cw, 128);

    const float sl2 = 0.08838834764831845f * 1.4426950408889634f;
    float o[64];
#pragma unroll
    for (int i = 0; i < 64; i++) o[i] = 0.f;
    float m0 = -INFINITY, m1 = -INFINITY, l0 = 0.f, l1 = 0.f;
    uint32_t p[32];
    float (&s)[64] = acc;

    auto issue_qk = [&](int st) {
#pragma unroll
      for (int kk = 0; kk < 8; kk++) {
        uint32_t off = (kk >> 2) * 16384 + (kk & 3) * 32;
        uint64_t da = make_desc(sQ + cw * 8192 + off, 16, 1024);
        uint64_t db = make_desc(sK + st * 32768 + off, 16, 1024);
        wgmma_m64n128k16_ss<0>(s, da, db, kk != 0);
      }
    };
    auto issue_pv = [&](int st) {
#pragma unroll
      for (int kk = 0; kk < 8; kk++) {
        uint64_t db = make_desc(sV + st * 32768 + kk * 2048, 16384, 1024);
        wgmma_m64n128k16_rs<1>(o, p[kk * 4 + 0], p[kk * 4 + 1], p[kk * 4 + 2], p[kk * 4 + 3], db, 1);
      }
    };
    auto softmax = [&](float& sc0, float& sc1) {
      float mx0 = m0, mx1 = m1;
#pragma unroll
      for (int j = 0; j < 16; j++) {
        mx0 = fmaxf(mx0, fmaxf(s[j * 4 + 0], s[j * 4 + 1]));
        mx1 = fmaxf(mx1, fmaxf(s[j * 4 + 2], s[j * 4 + 3]));
      }
      mx0 = fmaxf(mx0, __shfl_xor_sync(0xffffffffu, mx0, 1));
      mx0 = fmaxf(mx0, __shfl_xor_sync(0xffffffffu, mx0, 2));
      mx1 = fmaxf(mx1, __shfl_xor_sync(0xffffffffu, mx1, 1));
      mx1 = fmaxf(mx1, __shfl_xor_sync(0xffffffffu, mx1, 2));
      float ms0 = mx0 * sl2, ms1 = mx1 * sl2;
      sc0 = ex2(m0 * sl2 - ms0);
      sc1 = ex2(m1 * sl2 - ms1);
      m0 = mx0; m1 = mx1;
      float r0 = 0.f, r1 = 0.f;
#pragma unroll
      for (int j = 0; j < 16; j++) {
        s[j * 4 + 0] = ex2(fmaf(s[j * 4 + 0], sl2, -ms0));
        s[j * 4 + 1] = ex2(fmaf(s[j * 4 + 1], sl2, -ms0));
        s[j * 4 + 2] = ex2(fmaf(s[j * 4 + 2], sl2, -ms1));
        s[j * 4 + 3] = ex2(fmaf(s[j * 4 + 3], sl2, -ms1));
        r0 += s[j * 4 + 0] + s[j * 4 + 1];
        r1 += s[j * 4 + 2] + s[j * 4 + 3];
      }
      l0 = l0 * sc0 + r0;
      l1 = l1 * sc1 + r1;
    };
    auto cvt_p = [&]() {
#pragma unroll
      for (int kk = 0; kk < 8; kk++) {
        p[kk * 4 + 0] = pack_bf16(s[kk * 8 + 0], s[kk * 8 + 1]);
        p[kk * 4 + 1] = pack_bf16(s[kk * 8 + 2], s[kk * 8 + 3]);
        p[kk * 4 + 2] = pack_bf16(s[kk * 8 + 4], s[kk * 8 + 5]);
        p[kk * 4 + 3] = pack_bf16(s[kk * 8 + 6], s[kk * 8 + 7]);
      }
    };

    if (cw == 0) named_bar_arrive(3, 256);
    {
      const int it = 4, st = 0;
      mbar_wait(fullK(st), (it >> 1) & 1);
      named_bar_sync(3 + cw, 256);
      wgmma_fence();
      issue_qk(st);
      wgmma_commit();
      named_bar_arrive(3 + (cw ^ 1), 256);
      wgmma_wait<0>();
      if (lane == 0) mbar_arrive(emptyK(st));
      float sc0, sc1;
      softmax(sc0, sc1);
      cvt_p();
    }
    for (int n = 1; n < 16; n++) {
      const int it = 4 + n, st = it & 1;
      const int itv = it - 1, stv = itv & 1;
      mbar_wait(fullK(st), (it >> 1) & 1);
      named_bar_sync(3 + cw, 256);
      wgmma_fence();
      issue_qk(st);
      wgmma_commit();
      mbar_wait(fullV(stv), (itv >> 1) & 1);
      issue_pv(stv);
      wgmma_commit();
      named_bar_arrive(3 + (cw ^ 1), 256);
      wgmma_wait<1>();
      if (lane == 0) mbar_arrive(emptyK(st));
      float sc0, sc1;
      softmax(sc0, sc1);
      wgmma_wait<0>();
      if (lane == 0) mbar_arrive(emptyV(stv));
#pragma unroll
      for (int j = 0; j < 16; j++) {
        o[j * 4 + 0] *= sc0; o[j * 4 + 1] *= sc0;
        o[j * 4 + 2] *= sc1; o[j * 4 + 3] *= sc1;
      }
      cvt_p();
    }
    {
      const int itv = 19, stv = itv & 1;
      mbar_wait(fullV(stv), (itv >> 1) & 1);
      wgmma_fence();
      issue_pv(stv);
      wgmma_commit();
      wgmma_wait<0>();
    }
    if (cw == 1) {   }
    l0 += __shfl_xor_sync(0xffffffffu, l0, 1); l0 += __shfl_xor_sync(0xffffffffu, l0, 2);
    l1 += __shfl_xor_sync(0xffffffffu, l1, 1); l1 += __shfl_xor_sync(0xffffffffu, l1, 2);
    store_acc_sw128(sQ, cw, o, 1.0f / l0, 1.0f / l1);
    fence_proxy_async();
    named_bar_sync(1 + cw, 128);
    if ((threadIdx.x & 127) == 0) {
      tma_store_2d(&tm_o, sQ + cw * 8192, n0, mt * 128 + cw * 64);
      tma_store_2d(&tm_o, sQ + 16384 + cw * 8192, n0 + 64, mt * 128 + cw * 64);
      tma_store_commit();
      tma_store_wait_read();
    }
  }
}

constexpr int F_STAGES = 6;
constexpr int F_STAGE_BYTES = 16384 + 8192;
constexpr int F_SMEM = F_STAGES * F_STAGE_BYTES + 256 + 1024;
constexpr int F_KS = HD / 64;
constexpr int F_KH = (FF + 63) / 64;

__global__ void __launch_bounds__(384, 1)
final_kernel(const __grid_constant__ CUtensorMap tm_o, const __grid_constant__ CUtensorMap tm_wo,
             const __grid_constant__ CUtensorMap tm_h, const __grid_constant__ CUtensorMap tm_w2,
             const bf16* __restrict__ x, const bf16* __restrict__ b2, bf16* __restrict__ out) {
  extern __shared__ uint8_t smem_raw[];
  uint32_t sb = (smem_u32(smem_raw) + 1023) & ~1023u;
  const uint32_t sBar = sb + F_STAGES * F_STAGE_BYTES;
  const int mt = blockIdx.x >> 3, nt = blockIdx.x & 7;
  const int wg = threadIdx.x >> 7;
  if (threadIdx.x == 0) {
    for (int s = 0; s < F_STAGES; s++) { mbar_init(sBar + 8 * s, 1); mbar_init(sBar + 64 + 8 * s, 8); }
    asm volatile("fence.mbarrier_init.release.cluster;" ::: "memory");
  }
  __syncthreads();
  if (wg == 0) {
    reg_dealloc<24>();
    if (threadIdx.x == 0) {
      for (int k = 0; k < F_KS + F_KH; k++) {
        int st = k % F_STAGES, ph = (k / F_STAGES) & 1;
        mbar_wait(sBar + 64 + 8 * st, ph ^ 1);
        uint32_t buf = sb + st * F_STAGE_BYTES;
        mbar_expect_tx(sBar + 8 * st, F_STAGE_BYTES);
        if (k < F_KS) {
          tma_load_2d(buf, &tm_o, sBar + 8 * st, k * 64, mt * 128);
          tma_load_2d(buf + 16384, &tm_wo, sBar + 8 * st, nt * 64, k * 64);
        } else {
          tma_load_2d(buf, &tm_h, sBar + 8 * st, (k - F_KS) * 64, mt * 128);
          tma_load_2d(buf + 16384, &tm_w2, sBar + 8 * st, nt * 64, (k - F_KS) * 64);
        }
      }
    }
  } else {
    reg_alloc<240>();
    const int cw = wg - 1;
    const int lane = threadIdx.x & 31;
    float accS[32], accB[32];
#pragma unroll
    for (int i = 0; i < 32; i++) { accS[i] = 0.f; accB[i] = 0.f; }
    for (int k = 0; k < F_KS; k++) {
      int st = k % F_STAGES, ph = (k / F_STAGES) & 1;
      uint32_t buf = sb + st * F_STAGE_BYTES;
      mbar_wait(sBar + 8 * st, ph);
      wgmma_fence();
#pragma unroll
      for (int kk = 0; kk < 4; kk++)
        wgmma_m64n64k16_ss<1>(accS, make_desc(buf + cw * 8192 + kk * 32, 16, 1024),
                              make_desc(buf + 16384 + kk * 2048, 8192, 1024), 1);
      wgmma_commit();
      wgmma_wait<0>();
      if (lane == 0) mbar_arrive(sBar + 64 + 8 * st);
    }
    for (int k = F_KS; k < F_KS + F_KH; k++) {
      int st = k % F_STAGES, ph = (k / F_STAGES) & 1;
      uint32_t buf = sb + st * F_STAGE_BYTES;
      mbar_wait(sBar + 8 * st, ph);
      wgmma_fence();
#pragma unroll
      for (int kk = 0; kk < 4; kk++)
        wgmma_m64n64k16_ss<1>(accB, make_desc(buf + cw * 8192 + kk * 32, 16, 1024),
                              make_desc(buf + 16384 + kk * 2048, 8192, 1024), 1);
      wgmma_commit();
      wgmma_wait<0>();
      if (lane == 0) mbar_arrive(sBar + 64 + 8 * st);
    }
    const int warp = (threadIdx.x >> 5) & 3;
    const int r0 = mt * 128 + cw * 64 + warp * 16 + (lane >> 2);
#pragma unroll
    for (int j = 0; j < 8; j++) {
      int col = nt * 64 + j * 8 + (lane & 3) * 2;
      float bb0 = __bfloat162float(b2[col]), bb1 = __bfloat162float(b2[col + 1]);
#pragma unroll
      for (int hh = 0; hh < 2; hh++) {
        int row = r0 + hh * 8;
        uint32_t xv = *reinterpret_cast<const uint32_t*>(x + row * DM + col);
        float x0 = __uint_as_float(xv << 16), x1 = __uint_as_float(xv & 0xffff0000u);
        float g0 = accB[j * 4 + hh * 2 + 0] + bb0, g1 = accB[j * 4 + hh * 2 + 1] + bb1;
        g0 = g0 / (1.0f + __expf(-g0));
        g1 = g1 / (1.0f + __expf(-g1));
        float o0 = x0 + accS[j * 4 + hh * 2 + 0] * g0;
        float o1 = x1 + accS[j * 4 + hh * 2 + 1] * g1;
        *reinterpret_cast<uint32_t*>(out + row * DM + col) = pack_bf16(o0, o1);
      }
    }
  }
}

typedef CUresult (*PFN_encodeTiled)(CUtensorMap*, CUtensorMapDataType, cuuint32_t, void*, const cuuint64_t*,
                                    const cuuint64_t*, const cuuint32_t*, const cuuint32_t*, CUtensorMapInterleave,
                                    CUtensorMapSwizzle, CUtensorMapL2promotion, CUtensorMapFloatOOBfill);

static void make_tm(PFN_encodeTiled enc, CUtensorMap* tm, const void* ptr, uint64_t cols, uint64_t rows,
                    uint32_t box_c, uint32_t box_r) {
  cuuint64_t dims[2] = {cols, rows};
  cuuint64_t strides[1] = {cols * 2};
  cuuint32_t box[2] = {box_c, box_r};
  cuuint32_t es[2] = {1, 1};
  enc(tm, CU_TENSOR_MAP_DATA_TYPE_BFLOAT16, 2, const_cast<void*>(ptr), dims, strides, box, es,
      CU_TENSOR_MAP_INTERLEAVE_NONE, CU_TENSOR_MAP_SWIZZLE_128B, CU_TENSOR_MAP_L2_PROMOTION_L2_256B,
      CU_TENSOR_MAP_FLOAT_OOB_FILL_NONE);
}

extern "C" void kernel_launch(void* const* d_in, const int* in_sizes, int n_in, void* d_out, int out_size) {
  const bf16* x = (const bf16*)d_in[0];
  const bf16* kc = (const bf16*)d_in[1];
  const bf16* vc = (const bf16*)d_in[2];
  const bf16* wq = (const bf16*)d_in[3];
  const bf16* wo = (const bf16*)d_in[4];
  const bf16* w1 = (const bf16*)d_in[6];
  const bf16* b1 = (const bf16*)d_in[7];
  const bf16* w2 = (const bf16*)d_in[8];
  const bf16* b2 = (const bf16*)d_in[9];
  bf16* out = (bf16*)d_out;

  CUtensorMap tm_xn, tm_y, tm_wq, tm_w1, tm_k, tm_v, tm_ost, tm_hst, tm_old, tm_hld, tm_wo, tm_w2;
  {
    void* fn = nullptr;
    cudaDriverEntryPointQueryResult qres;
    cudaGetDriverEntryPoint("cuTensorMapEncodeTiled", &fn, cudaEnableDefault, &qres);
    PFN_encodeTiled enc = (PFN_encodeTiled)fn;
    void *p_xn, *p_y, *p_o, *p_h;
    cudaGetSymbolAddress(&p_xn, g_xn);
    cudaGetSymbolAddress(&p_y, g_y);
    cudaGetSymbolAddress(&p_o, g_o);
    cudaGetSymbolAddress(&p_h, g_h);
    make_tm(enc, &tm_xn, p_xn, DM, SQ, 64, 128);
    make_tm(enc, &tm_y, p_y, DM, SQ, 64, 128);
    make_tm(enc, &tm_wq, wq, HD, DM, 64, 64);
    make_tm(enc, &tm_w1, w1, FF, DM, 64, 64);
    make_tm(enc, &tm_k, kc, DH, (uint64_t)NH * SQ, 64, 128);
    make_tm(enc, &tm_v, vc, DH, (uint64_t)NH * SQ, 64, 128);
    make_tm(enc, &tm_ost, p_o, HD, SQ, 64, 64);
    make_tm(enc, &tm_hst, p_h, FF, SQ, 64, 64);
    make_tm(enc, &tm_old, p_o, HD, SQ, 64, 128);
    make_tm(enc, &tm_hld, p_h, FF, SQ, 64, 128);
    make_tm(enc, &tm_wo, wo, DM, HD, 64, 64);
    make_tm(enc, &tm_w2, w2, DM, FF, 64, 64);
    cudaFuncSetAttribute(attn_kernel, cudaFuncAttributeMaxDynamicSharedMemorySize, ATT_SMEM);
    cudaFuncSetAttribute(final_kernel, cudaFuncAttributeMaxDynamicSharedMemorySize, F_SMEM);
  }
  ln_kernel<<<SQ / 8, 256>>>(x);
  attn_kernel<<<ATT_CTAS + MLP1_CTAS, 384, ATT_SMEM>>>(tm_xn, tm_y, tm_wq, tm_w1, tm_k, tm_v, tm_ost, tm_hst, b1);
  final_kernel<<<128, 384, F_SMEM>>>(tm_old, tm_wo, tm_hld, tm_w2, x, b2, out);
}
```

```cpp
#include <cuda_runtime.h>
#include <cuda_bf16.h>
#include <cuda.h>
#include <stdint.h>

typedef __nv_bfloat16 bf16;

constexpr int SQ = 2048, DM = 512, NH = 32, DH = 128, FF = 1376, HD = 4096;

__device__ __align__(1024) bf16 g_xn[SQ * DM];
__device__ __align__(1024) bf16 g_y[SQ * DM];
__device__ __align__(1024) bf16 g_o[SQ * HD];
__device__ __align__(1024) bf16 g_h[SQ * FF];

__device__ __forceinline__ uint32_t smem_u32(const void* p) { return (uint32_t)__cvta_generic_to_shared(p); }
__device__ __forceinline__ void mbar_init(uint32_t bar, uint32_t count) {
  asm volatile("mbarrier.init.shared::cta.b64 [%0], %1;" ::"r"(bar), "r"(count));
}
__device__ __forceinline__ void mbar_expect_tx(uint32_t bar, uint32_t bytes) {
  asm volatile("mbarrier.arrive.expect_tx.shared::cta.b64 _, [%0], %1;" ::"r"(bar), "r"(bytes) : "memory");
}
__device__ __forceinline__ void mbar_arrive(uint32_t bar) {
  asm volatile("mbarrier.arrive.shared::cta.b64 _, [%0];" ::"r"(bar) : "memory");
}
__device__ __forceinline__ void mbar_wait(uint32_t bar, uint32_t parity) {
  asm volatile(
      "{\n.reg .pred P1;\n"
      "LAB_WAIT:\n"
      "mbarrier.try_wait.parity.shared::cta.b64 P1, [%0], %1;\n"
      "@P1 bra DONE;\n"
      "bra LAB_WAIT;\n"
      "DONE:\n}\n" ::"r"(bar), "r"(parity) : "memory");
}
__device__ __forceinline__ void tma_load_2d(uint32_t dst, const CUtensorMap* tm, uint32_t bar, int c0, int c1) {
  asm volatile(
      "cp.async.bulk.tensor.2d.shared::cluster.global.mbarrier::complete_tx::bytes [%0], [%1, {%3, %4}], [%2];"
      ::"r"(dst), "l"((uint64_t)tm), "r"(bar), "r"(c0), "r"(c1) : "memory");
}
__device__ __forceinline__ void tma_store_2d(const CUtensorMap* tm, uint32_t src, int c0, int c1) {
  asm volatile("cp.async.bulk.tensor.2d.global.shared::cta.bulk_group [%0, {%2, %3}], [%1];"
               ::"l"((uint64_t)tm), "r"(src), "r"(c0), "r"(c1) : "memory");
}
__device__ __forceinline__ void tma_store_commit() { asm volatile("cp.async.bulk.commit_group;" ::: "memory"); }
__device__ __forceinline__ void tma_store_wait_read() { asm volatile("cp.async.bulk.wait_group.read 0;" ::: "memory"); }
__device__ __forceinline__ void fence_proxy_async() { asm volatile("fence.proxy.async.shared::cta;" ::: "memory"); }
__device__ __forceinline__ void named_bar_sync(int id, int n) { asm volatile("bar.sync %0, %1;" ::"r"(id), "r"(n) : "memory"); }
__device__ __forceinline__ void named_bar_arrive(int id, int n) { asm volatile("bar.arrive %0, %1;" ::"r"(id), "r"(n) : "memory"); }
__device__ __forceinline__ void wgmma_fence() { asm volatile("wgmma.fence.sync.aligned;" ::: "memory"); }
__device__ __forceinline__ void wgmma_commit() { asm volatile("wgmma.commit_group.sync.aligned;" ::: "memory"); }
template <int N> __device__ __forceinline__ void wgmma_wait() { asm volatile("wgmma.wait_group.sync.aligned %0;" ::"n"(N) : "memory"); }
template <int R> __device__ __forceinline__ void reg_alloc() { asm volatile("setmaxnreg.inc.sync.aligned.u32 %0;" ::"n"(R)); }
template <int R> __device__ __forceinline__ void reg_dealloc() { asm volatile("setmaxnreg.dec.sync.aligned.u32 %0;" ::"n"(R)); }

__device__ __forceinline__ uint64_t make_desc(uint32_t addr, uint32_t lbo_bytes, uint32_t sbo_bytes) {
  return (uint64_t)((addr & 0x3FFFF) >> 4) | ((uint64_t)(lbo_bytes >> 4) << 16) | ((uint64_t)(sbo_bytes >> 4) << 32) |
         ((uint64_t)1 << 62);
}
__device__ __forceinline__ uint32_t pack_bf16(float lo, float hi) {
  uint32_t r;
  asm("cvt.rn.bf16x2.f32 %0, %1, %2;" : "=r"(r) : "f"(hi), "f"(lo));
  return r;
}
__device__ __forceinline__ float ex2(float x) {
  float y;
  asm("ex2.approx.ftz.f32 %0, %1;" : "=f"(y) : "f"(x));
  return y;
}

template<int TB> __device__ __forceinline__ void wgmma_m64n64k16_ss(float (&d)[32], uint64_t da, uint64_t db, int scaleD) {
  asm volatile("{\n.reg .pred p;\nsetp.ne.b32 p, %34, 0;\n"
    "wgmma.mma_async.sync.aligned.m64n64k16.f32.bf16.bf16 {%0, %1, %2, %3, %4, %5, %6, %7, %8, %9, %10, %11, %12, %13, %14, %15, %16, %17, %18, %19, %20, %21, %22, %23, %24, %25, %26, %27, %28, %29, %30, %31}, %32, %33, p, 1, 1, 0, %35;\n}\n"
    : "+f"(d[0]), "+f"(d[1]), "+f"(d[2]), "+f"(d[3]), "+f"(d[4]), "+f"(d[5]), "+f"(d[6]), "+f"(d[7]), "+f"(d[8]), "+f"(d[9]), "+f"(d[10]), "+f"(d[11]), "+f"(d[12]), "+f"(d[13]), "+f"(d[14]), "+f"(d[15]), "+f"(d[16]), "+f"(d[17]), "+f"(d[18]), "+f"(d[19]), "+f"(d[20]), "+f"(d[21]), "+f"(d[22]), "+f"(d[23]), "+f"(d[24]), "+f"(d[25]), "+f"(d[26]), "+f"(d[27]), "+f"(d[28]), "+f"(d[29]), "+f"(d[30]), "+f"(d[31])
    : "l"(da), "l"(db), "r"(scaleD), "n"(TB));
}
template<int TB> __device__ __forceinline__ void wgmma_m64n128k16_ss(float (&d)[64], uint64_t da, uint64_t db, int scaleD) {
  asm volatile("{\n.reg .pred p;\nsetp.ne.b32 p, %66, 0;\n"
    "wgmma.mma_async.sync.aligned.m64n128k16.f32.bf16.bf16 {%0, %1, %2, %3, %4, %5, %6, %7, %8, %9, %10, %11, %12, %13, %14, %15, %16, %17, %18, %19, %20, %21, %22, %23, %24, %25, %26, %27, %28, %29, %30, %31, %32, %33, %34, %35, %36, %37, %38, %39, %40, %41, %42, %43, %44, %45, %46, %47, %48, %49, %50, %51, %52, %53, %54, %55, %56, %57, %58, %59, %60, %61, %62, %63}, %64, %65, p, 1, 1, 0, %67;\n}\n"
    : "+f"(d[0]), "+f"(d[1]), "+f"(d[2]), "+f"(d[3]), "+f"(d[4]), "+f"(d[5]), "+f"(d[6]), "+f"(d[7]), "+f"(d[8]), "+f"(d[9]), "+f"(d[10]), "+f"(d[11]), "+f"(d[12]), "+f"(d[13]), "+f"(d[14]), "+f"(d[15]), "+f"(d[16]), "+f"(d[17]), "+f"(d[18]), "+f"(d[19]), "+f"(d[20]), "+f"(d[21]), "+f"(d[22]), "+f"(d[23]), "+f"(d[24]), "+f"(d[25]), "+f"(d[26]), "+f"(d[27]), "+f"(d[28]), "+f"(d[29]), "+f"(d[30]), "+f"(d[31]), "+f"(d[32]), "+f"(d[33]), "+f"(d[34]), "+f"(d[35]), "+f"(d[36]), "+f"(d[37]), "+f"(d[38]), "+f"(d[39]), "+f"(d[40]), "+f"(d[41]), "+f"(d[42]), "+f"(d[43]), "+f"(d[44]), "+f"(d[45]), "+f"(d[46]), "+f"(d[47]), "+f"(d[48]), "+f"(d[49]), "+f"(d[50]), "+f"(d[51]), "+f"(d[52]), "+f"(d[53]), "+f"(d[54]), "+f"(d[55]), "+f"(d[56]), "+f"(d[57]), "+f"(d[58]), "+f"(d[59]), "+f"(d[60]), "+f"(d[61]), "+f"(d[62]), "+f"(d[63])
    : "l"(da), "l"(db), "r"(scaleD), "n"(TB));
}
template<int TB> __device__ __forceinline__ void wgmma_m64n128k16_rs(float (&d)[64], uint32_t a0, uint32_t a1, uint32_t a2, uint32_t a3, uint64_t db, int scaleD) {
  asm volatile("{\n.reg .pred p;\nsetp.ne.b32 p, %69, 0;\n"
    "wgmma.mma_async.sync.aligned.m64n128k16.f32.bf16.bf16 {%0, %1, %2, %3, %4, %5, %6, %7, %8, %9, %10, %11, %12, %13, %14, %15, %16, %17, %18, %19, %20, %21, %22, %23, %24, %25, %26, %27, %28, %29, %30, %31, %32, %33, %34, %35, %36, %37, %38, %39, %40, %41, %42, %43, %44, %45, %46, %47, %48, %49, %50, %51, %52, %53, %54, %55, %56, %57, %58, %59, %60, %61, %62, %63}, {%64, %65, %66, %67}, %68, p, 1, 1, %70;\n}\n"
    : "+f"(d[0]), "+f"(d[1]), "+f"(d[2]), "+f"(d[3]), "+f"(d[4]), "+f"(d[5]), "+f"(d[6]), "+f"(d[7]), "+f"(d[8]), "+f"(d[9]), "+f"(d[10]), "+f"(d[11]), "+f"(d[12]), "+f"(d[13]), "+f"(d[14]), "+f"(d[15]), "+f"(d[16]), "+f"(d[17]), "+f"(d[18]), "+f"(d[19]), "+f"(d[20]), "+f"(d[21]), "+f"(d[22]), "+f"(d[23]), "+f"(d[24]), "+f"(d[25]), "+f"(d[26]), "+f"(d[27]), "+f"(d[28]), "+f"(d[29]), "+f"(d[30]), "+f"(d[31]), "+f"(d[32]), "+f"(d[33]), "+f"(d[34]), "+f"(d[35]), "+f"(d[36]), "+f"(d[37]), "+f"(d[38]), "+f"(d[39]), "+f"(d[40]), "+f"(d[41]), "+f"(d[42]), "+f"(d[43]), "+f"(d[44]), "+f"(d[45]), "+f"(d[46]), "+f"(d[47]), "+f"(d[48]), "+f"(d[49]), "+f"(d[50]), "+f"(d[51]), "+f"(d[52]), "+f"(d[53]), "+f"(d[54]), "+f"(d[55]), "+f"(d[56]), "+f"(d[57]), "+f"(d[58]), "+f"(d[59]), "+f"(d[60]), "+f"(d[61]), "+f"(d[62]), "+f"(d[63])
    : "r"(a0), "r"(a1), "r"(a2), "r"(a3), "l"(db), "r"(scaleD), "n"(TB));
}


__global__ void __launch_bounds__(256) ln_kernel(const bf16* __restrict__ x) {
  int row = blockIdx.x * 8 + (threadIdx.x >> 5);
  int lane = threadIdx.x & 31;
  asm volatile("griddepcontrol.launch_dependents;" ::: "memory");
  asm volatile("griddepcontrol.wait;" ::: "memory");
  const uint4* px = reinterpret_cast<const uint4*>(x + row * DM);
  float v[16];
#pragma unroll
  for (int i = 0; i < 2; i++) {
    uint4 u = px[lane + 32 * i];
    const uint32_t w[4] = {u.x, u.y, u.z, u.w};
#pragma unroll
    for (int j = 0; j < 4; j++) {
      v[i * 8 + j * 2] = __uint_as_float(w[j] << 16);
      v[i * 8 + j * 2 + 1] = __uint_as_float(w[j] & 0xffff0000u);
    }
  }
#pragma unroll
  for (int pass = 0; pass < 2; pass++) {
    float s = 0.f;
#pragma unroll
    for (int i = 0; i < 16; i++) s += v[i];
#pragma unroll
    for (int o = 16; o > 0; o >>= 1) s += __shfl_xor_sync(0xffffffffu, s, o);
    float m = s * (1.0f / DM);
    float q = 0.f;
#pragma unroll
    for (int i = 0; i < 16; i++) { float d = v[i] - m; q += d * d; }
#pragma unroll
    for (int o = 16; o > 0; o >>= 1) q += __shfl_xor_sync(0xffffffffu, q, o);
    float rs = rsqrtf(q * (1.0f / DM) + 1e-5f);
    uint32_t w[8];
#pragma unroll
    for (int i = 0; i < 8; i++) {
      float a = (v[2 * i] - m) * rs, b = (v[2 * i + 1] - m) * rs;
      w[i] = pack_bf16(a, b);
      v[2 * i] = __uint_as_float(w[i] << 16);
      v[2 * i + 1] = __uint_as_float(w[i] & 0xffff0000u);
    }
    uint4* pd = reinterpret_cast<uint4*>((pass == 0 ? g_xn : g_y) + row * DM);
    pd[lane] = make_uint4(w[0], w[1], w[2], w[3]);
    pd[lane + 32] = make_uint4(w[4], w[5], w[6], w[7]);
  }
}

constexpr int ATT_CTAS = NH * (SQ / 128);
constexpr int MLP1_NT = (FF + 127) / 128;
constexpr int MLP1_CTAS = (SQ / 128) * MLP1_NT;
constexpr int SM_Q = 0, SM_K = 32768, SM_V = 32768 + 65536, SM_BAR = 32768 + 131072;
constexpr int ATT_SMEM = SM_BAR + 128 + 1024;

__device__ __forceinline__ void store_acc_sw128(uint32_t sbase, int cw, const float (&acc)[64], float mul0, float mul1) {
  int t = threadIdx.x & 127;
  int warp = t >> 5, lane = t & 31;
  int r0 = cw * 64 + warp * 16 + (lane >> 2);
#pragma unroll
  for (int j = 0; j < 16; j++) {
    int col = j * 8 + (lane & 3) * 2;
    int chunk = col >> 6;
    int g = (col & 63) >> 3;
    uint32_t a0 = sbase + chunk * 16384 + r0 * 128 + ((g ^ (r0 & 7)) << 4) + (col & 7) * 2;
    uint32_t a1 = a0 + 8 * 128;
    uint32_t p0 = pack_bf16(acc[j * 4 + 0] * mul0, acc[j * 4 + 1] * mul0);
    uint32_t p1 = pack_bf16(acc[j * 4 + 2] * mul1, acc[j * 4 + 3] * mul1);
    asm volatile("st.shared.b32 [%0], %1;" ::"r"(a0), "r"(p0) : "memory");
    asm volatile("st.shared.b32 [%0], %1;" ::"r"(a1), "r"(p1) : "memory");
  }
}

__device__ __forceinline__ float gelu_tanh(float x) {
  const float k0 = 0.7978845608028654f, k1 = 0.044715f;
  float u = k0 * (x + k1 * x * x * x);
  float t = tanhf(u);
  return 0.5f * x * (1.0f + t);
}

__global__ void __launch_bounds__(384, 1)
attn_kernel(const __grid_constant__ CUtensorMap tm_xn, const __grid_constant__ CUtensorMap tm_y,
            const __grid_constant__ CUtensorMap tm_wq, const __grid_constant__ CUtensorMap tm_w1,
            const __grid_constant__ CUtensorMap tm_k, const __grid_constant__ CUtensorMap tm_v,
            const __grid_constant__ CUtensorMap tm_o, const __grid_constant__ CUtensorMap tm_h,
            const bf16* __restrict__ b1) {
  extern __shared__ uint8_t smem_raw[];
  uint32_t sb = (smem_u32(smem_raw) + 1023) & ~1023u;
  const uint32_t sQ = sb + SM_Q, sK = sb + SM_K, sV = sb + SM_V, sBar = sb + SM_BAR;
  auto fullK = [&](int s) { return sBar + 8 * s; };
  auto fullV = [&](int s) { return sBar + 16 + 8 * s; };
  auto emptyK = [&](int s) { return sBar + 32 + 8 * s; };
  auto emptyV = [&](int s) { return sBar + 48 + 8 * s; };

  const bool is_mlp = blockIdx.x >= ATT_CTAS;
  int head, mt, n0;
  if (!is_mlp) { head = blockIdx.x >> 4; mt = blockIdx.x & 15; n0 = head * 128; }
  else { int i = blockIdx.x - ATT_CTAS; mt = i & 15; head = 0; n0 = (i >> 4) * 128; }

  const int wg = threadIdx.x >> 7;
  if (threadIdx.x == 0) {
    for (int s = 0; s < 2; s++) {
      mbar_init(fullK(s), 1); mbar_init(fullV(s), 1);
      mbar_init(emptyK(s), 8); mbar_init(emptyV(s), 8);
    }
    asm volatile("fence.mbarrier_init.release.cluster;" ::: "memory");
  }
  __syncthreads();
  asm volatile("griddepcontrol.launch_dependents;" ::: "memory");
  asm volatile("griddepcontrol.wait;" ::: "memory");

  if (wg == 0) {
    reg_dealloc<24>();
    if (threadIdx.x == 0) {
      const CUtensorMap* ta = is_mlp ? &tm_y : &tm_xn;
      const CUtensorMap* tb = is_mlp ? &tm_w1 : &tm_wq;
      for (int c = 0; c < 8; c++) {
        int it = c >> 1, st = it & 1;
        uint32_t buf = ((c & 1) ? sV : sK) + st * 32768;
        uint32_t fb = (c & 1) ? fullV(st) : fullK(st);
        uint32_t eb = (c & 1) ? emptyV(st) : emptyK(st);
        mbar_wait(eb, ((it >> 1) & 1) ^ 1);
        mbar_expect_tx(fb, 32768);
        tma_load_2d(buf, ta, fb, c * 64, mt * 128);
        tma_load_2d(buf + 16384, tb, fb, n0, c * 64);
        tma_load_2d(buf + 24576, tb, fb, n0 + 64, c * 64);
      }
      if (!is_mlp) {
        for (int n = 0; n < 16; n++) {
          int it = 4 + n, st = it & 1;
          uint32_t ph = ((it >> 1) & 1) ^ 1;
          int row = head * SQ + n * 128;
          mbar_wait(emptyK(st), ph);
          mbar_expect_tx(fullK(st), 32768);
          tma_load_2d(sK + st * 32768, &tm_k, fullK(st), 0, row);
          tma_load_2d(sK + st * 32768 + 16384, &tm_k, fullK(st), 64, row);
          mbar_wait(emptyV(st), ph);
          mbar_expect_tx(fullV(st), 32768);
          tma_load_2d(sV + st * 32768, &tm_v, fullV(st), 0, row);
          tma_load_2d(sV + st * 32768 + 16384, &tm_v, fullV(st), 64, row);
        }
      }
    }
  } else {
    reg_alloc<240>();
    const int cw = wg - 1;
    const int lane = threadIdx.x & 31;
    float acc[64];
#pragma unroll
    for (int i = 0; i < 64; i++) acc[i] = 0.f;
    for (int c = 0; c < 8; c++) {
      int it = c >> 1, st = it & 1;
      uint32_t buf = ((c & 1) ? sV : sK) + st * 32768;
      uint32_t fb = (c & 1) ? fullV(st) : fullK(st);
      uint32_t eb = (c & 1) ? emptyV(st) : emptyK(st);
      mbar_wait(fb, (it >> 1) & 1);
      wgmma_fence();
#pragma unroll
      for (int kk = 0; kk < 4; kk++) {
        uint64_t da = make_desc(buf + cw * 8192 + kk * 32, 16, 1024);
        uint64_t db = make_desc(buf + 16384 + kk * 2048, 8192, 1024);
        wgmma_m64n128k16_ss<1>(acc, da, db, 1);
      }
      wgmma_commit();
      wgmma_wait<0>();
      if (lane == 0) mbar_arrive(eb);
    }
    if (is_mlp) {
      int t = threadIdx.x & 127;
      int cbase = n0 + (lane & 3) * 2;
#pragma unroll
      for (int j = 0; j < 16; j++) {
        int col = cbase + j * 8;
        float bb0 = 0.f, bb1 = 0.f;
        if (col < FF) { bb0 = __bfloat162float(b1[col]); bb1 = __bfloat162float(b1[col + 1]); }
        acc[j * 4 + 0] = gelu_tanh(acc[j * 4 + 0] + bb0);
        acc[j * 4 + 1] = gelu_tanh(acc[j * 4 + 1] + bb1);
        acc[j * 4 + 2] = gelu_tanh(acc[j * 4 + 2] + bb0);
        acc[j * 4 + 3] = gelu_tanh(acc[j * 4 + 3] + bb1);
      }
      store_acc_sw128(sQ, cw, acc, 1.f, 1.f);
      fence_proxy_async();
      named_bar_sync(1 + cw, 128);
      if (t == 0) {
        tma_store_2d(&tm_h, sQ + cw * 8192, n0, mt * 128 + cw * 64);
        if (n0 + 64 < FF) tma_store_2d(&tm_h, sQ + 16384 + cw * 8192, n0 + 64, mt * 128 + cw * 64);
        tma_store_commit();
        tma_store_wait_read();
      }
      return;
    }
    store_acc_sw128(sQ, cw, acc, 1.f, 1.f);
    fence_proxy_async();
    named_bar_sync(1 + cw, 128);

    const float sl2 = 0.08838834764831845f * 1.4426950408889634f;
    float o[64];
#pragma unroll
    for (int i = 0; i < 64; i++) o[i] = 0.f;
    float m0 = -INFINITY, m1 = -INFINITY, l0 = 0.f, l1 = 0.f;
    uint32_t p[32];
    float (&s)[64] = acc;

    auto issue_qk = [&](int st) {
#pragma unroll
      for (int kk = 0; kk < 8; kk++) {
        uint32_t off = (kk >> 2) * 16384 + (kk & 3) * 32;
        uint64_t da = make_desc(sQ + cw * 8192 + off, 16, 1024);
        uint64_t db = make_desc(sK + st * 32768 + off, 16, 1024);
        wgmma_m64n128k16_ss<0>(s, da, db, kk != 0);
      }
    };
    auto issue_pv = [&](int st) {
#pragma unroll
      for (int kk = 0; kk < 8; kk++) {
        uint64_t db = make_desc(sV + st * 32768 + kk * 2048, 16384, 1024);
        wgmma_m64n128k16_rs<1>(o, p[kk * 4 + 0], p[kk * 4 + 1], p[kk * 4 + 2], p[kk * 4 + 3], db, 1);
      }
    };
    auto softmax = [&](float& sc0, float& sc1) {
      float mx0 = m0, mx1 = m1;
#pragma unroll
      for (int j = 0; j < 16; j++) {
        mx0 = fmaxf(mx0, fmaxf(s[j * 4 + 0], s[j * 4 + 1]));
        mx1 = fmaxf(mx1, fmaxf(s[j * 4 + 2], s[j * 4 + 3]));
      }
      mx0 = fmaxf(mx0, __shfl_xor_sync(0xffffffffu, mx0, 1));
      mx0 = fmaxf(mx0, __shfl_xor_sync(0xffffffffu, mx0, 2));
      mx1 = fmaxf(mx1, __shfl_xor_sync(0xffffffffu, mx1, 1));
      mx1 = fmaxf(mx1, __shfl_xor_sync(0xffffffffu, mx1, 2));
      float ms0 = mx0 * sl2, ms1 = mx1 * sl2;
      sc0 = ex2(m0 * sl2 - ms0);
      sc1 = ex2(m1 * sl2 - ms1);
      m0 = mx0; m1 = mx1;
      float r0 = 0.f, r1 = 0.f;
#pragma unroll
      for (int j = 0; j < 16; j++) {
        s[j * 4 + 0] = ex2(fmaf(s[j * 4 + 0], sl2, -ms0));
        s[j * 4 + 1] = ex2(fmaf(s[j * 4 + 1], sl2, -ms0));
        s[j * 4 + 2] = ex2(fmaf(s[j * 4 + 2], sl2, -ms1));
        s[j * 4 + 3] = ex2(fmaf(s[j * 4 + 3], sl2, -ms1));
        r0 += s[j * 4 + 0] + s[j * 4 + 1];
        r1 += s[j * 4 + 2] + s[j * 4 + 3];
      }
      l0 = l0 * sc0 + r0;
      l1 = l1 * sc1 + r1;
    };
    auto cvt_p = [&]() {
#pragma unroll
      for (int kk = 0; kk < 8; kk++) {
        p[kk * 4 + 0] = pack_bf16(s[kk * 8 + 0], s[kk * 8 + 1]);
        p[kk * 4 + 1] = pack_bf16(s[kk * 8 + 2], s[kk * 8 + 3]);
        p[kk * 4 + 2] = pack_bf16(s[kk * 8 + 4], s[kk * 8 + 5]);
        p[kk * 4 + 3] = pack_bf16(s[kk * 8 + 6], s[kk * 8 + 7]);
      }
    };

    if (cw == 0) named_bar_arrive(3, 256);
    {
      const int it = 4, st = 0;
      mbar_wait(fullK(st), (it >> 1) & 1);
      named_bar_sync(3 + cw, 256);
      wgmma_fence();
      issue_qk(st);
      wgmma_commit();
      named_bar_arrive(3 + (cw ^ 1), 256);
      wgmma_wait<0>();
      if (lane == 0) mbar_arrive(emptyK(st));
      float sc0, sc1;
      softmax(sc0, sc1);
      cvt_p();
    }
    for (int n = 1; n < 16; n++) {
      const int it = 4 + n, st = it & 1;
      const int itv = it - 1, stv = itv & 1;
      mbar_wait(fullK(st), (it >> 1) & 1);
      named_bar_sync(3 + cw, 256);
      wgmma_fence();
      issue_qk(st);
      wgmma_commit();
      mbar_wait(fullV(stv), (itv >> 1) & 1);
      issue_pv(stv);
      wgmma_commit();
      named_bar_arrive(3 + (cw ^ 1), 256);
      wgmma_wait<1>();
      if (lane == 0) mbar_arrive(emptyK(st));
      float sc0, sc1;
      softmax(sc0, sc1);
      wgmma_wait<0>();
      if (lane == 0) mbar_arrive(emptyV(stv));
#pragma unroll
      for (int j = 0; j < 16; j++) {
        o[j * 4 + 0] *= sc0; o[j * 4 + 1] *= sc0;
        o[j * 4 + 2] *= sc1; o[j * 4 + 3] *= sc1;
      }
      cvt_p();
    }
    {
      const int itv = 19, stv = itv & 1;
      mbar_wait(fullV(stv), (itv >> 1) & 1);
      wgmma_fence();
      issue_pv(stv);
      wgmma_commit();
      wgmma_wait<0>();
    }
    if (cw == 1) {   }
    l0 += __shfl_xor_sync(0xffffffffu, l0, 1); l0 += __shfl_xor_sync(0xffffffffu, l0, 2);
    l1 += __shfl_xor_sync(0xffffffffu, l1, 1); l1 += __shfl_xor_sync(0xffffffffu, l1, 2);
    store_acc_sw128(sQ, cw, o, 1.0f / l0, 1.0f / l1);
    fence_proxy_async();
    named_bar_sync(1 + cw, 128);
    if ((threadIdx.x & 127) == 0) {
      tma_store_2d(&tm_o, sQ + cw * 8192, n0, mt * 128 + cw * 64);
      tma_store_2d(&tm_o, sQ + 16384 + cw * 8192, n0 + 64, mt * 128 + cw * 64);
      tma_store_commit();
      tma_store_wait_read();
    }
  }
}

constexpr int F_STAGES = 6;
constexpr int F_STAGE_BYTES = 16384 + 8192;
constexpr int F_SMEM = F_STAGES * F_STAGE_BYTES + 256 + 1024;
constexpr int F_KS = HD / 64;
constexpr int F_KH = (FF + 63) / 64;

__global__ void __launch_bounds__(384, 1)
final_kernel(const __grid_constant__ CUtensorMap tm_o, const __grid_constant__ CUtensorMap tm_wo,
             const __grid_constant__ CUtensorMap tm_h, const __grid_constant__ CUtensorMap tm_w2,
             const bf16* __restrict__ x, const bf16* __restrict__ b2, bf16* __restrict__ out) {
  extern __shared__ uint8_t smem_raw[];
  uint32_t sb = (smem_u32(smem_raw) + 1023) & ~1023u;
  const uint32_t sBar = sb + F_STAGES * F_STAGE_BYTES;
  const int mt = blockIdx.x >> 3, nt = blockIdx.x & 7;
  const int wg = threadIdx.x >> 7;
  if (threadIdx.x == 0) {
    for (int s = 0; s < F_STAGES; s++) { mbar_init(sBar + 8 * s, 1); mbar_init(sBar + 64 + 8 * s, 8); }
    asm volatile("fence.mbarrier_init.release.cluster;" ::: "memory");
  }
  __syncthreads();
  asm volatile("griddepcontrol.launch_dependents;" ::: "memory");
  asm volatile("griddepcontrol.wait;" ::: "memory");
  if (wg == 0) {
    reg_dealloc<24>();
    if (threadIdx.x == 0) {
      for (int k = 0; k < F_KS + F_KH; k++) {
        int st = k % F_STAGES, ph = (k / F_STAGES) & 1;
        mbar_wait(sBar + 64 + 8 * st, ph ^ 1);
        uint32_t buf = sb + st * F_STAGE_BYTES;
        mbar_expect_tx(sBar + 8 * st, F_STAGE_BYTES);
        if (k < F_KS) {
          tma_load_2d(buf, &tm_o, sBar + 8 * st, k * 64, mt * 128);
          tma_load_2d(buf + 16384, &tm_wo, sBar + 8 * st, nt * 64, k * 64);
        } else {
          tma_load_2d(buf, &tm_h, sBar + 8 * st, (k - F_KS) * 64, mt * 128);
          tma_load_2d(buf + 16384, &tm_w2, sBar + 8 * st, nt * 64, (k - F_KS) * 64);
        }
      }
    }
  } else {
    reg_alloc<240>();
    const int cw = wg - 1;
    const int lane = threadIdx.x & 31;
    float accS[32], accB[32];
#pragma unroll
    for (int i = 0; i < 32; i++) { accS[i] = 0.f; accB[i] = 0.f; }
    for (int k = 0; k < F_KS; k++) {
      int st = k % F_STAGES, ph = (k / F_STAGES) & 1;
      uint32_t buf = sb + st * F_STAGE_BYTES;
      mbar_wait(sBar + 8 * st, ph);
      wgmma_fence();
#pragma unroll
      for (int kk = 0; kk < 4; kk++)
        wgmma_m64n64k16_ss<1>(accS, make_desc(buf + cw * 8192 + kk * 32, 16, 1024),
                              make_desc(buf + 16384 + kk * 2048, 8192, 1024), 1);
      wgmma_commit();
      wgmma_wait<1>();
      if (k > 0 && lane == 0) mbar_arrive(sBar + 64 + 8 * ((k - 1) % F_STAGES));
    }
    for (int k = F_KS; k < F_KS + F_KH; k++) {
      int st = k % F_STAGES, ph = (k / F_STAGES) & 1;
      uint32_t buf = sb + st * F_STAGE_BYTES;
      mbar_wait(sBar + 8 * st, ph);
      wgmma_fence();
#pragma unroll
      for (int kk = 0; kk < 4; kk++)
        wgmma_m64n64k16_ss<1>(accB, make_desc(buf + cw * 8192 + kk * 32, 16, 1024),
                              make_desc(buf + 16384 + kk * 2048, 8192, 1024), 1);
      wgmma_commit();
      wgmma_wait<1>();
      if (lane == 0) mbar_arrive(sBar + 64 + 8 * ((k - 1) % F_STAGES));
    }
    wgmma_wait<0>();
    const int warp = (threadIdx.x >> 5) & 3;
    const int r0 = mt * 128 + cw * 64 + warp * 16 + (lane >> 2);
#pragma unroll
    for (int j = 0; j < 8; j++) {
      int col = nt * 64 + j * 8 + (lane & 3) * 2;
      float bb0 = __bfloat162float(b2[col]), bb1 = __bfloat162float(b2[col + 1]);
#pragma unroll
      for (int hh = 0; hh < 2; hh++) {
        int row = r0 + hh * 8;
        uint32_t xv = *reinterpret_cast<const uint32_t*>(x + row * DM + col);
        float x0 = __uint_as_float(xv << 16), x1 = __uint_as_float(xv & 0xffff0000u);
        float g0 = accB[j * 4 + hh * 2 + 0] + bb0, g1 = accB[j * 4 + hh * 2 + 1] + bb1;
        g0 = g0 / (1.0f + __expf(-g0));
        g1 = g1 / (1.0f + __expf(-g1));
        float o0 = x0 + accS[j * 4 + hh * 2 + 0] * g0;
        float o1 = x1 + accS[j * 4 + hh * 2 + 1] * g1;
        *reinterpret_cast<uint32_t*>(out + row * DM + col) = pack_bf16(o0, o1);
      }
    }
  }
}

typedef CUresult (*PFN_encodeTiled)(CUtensorMap*, CUtensorMapDataType, cuuint32_t, void*, const cuuint64_t*,
                                    const cuuint64_t*, const cuuint32_t*, const cuuint32_t*, CUtensorMapInterleave,
                                    CUtensorMapSwizzle, CUtensorMapL2promotion, CUtensorMapFloatOOBfill);

static void make_tm(PFN_encodeTiled enc, CUtensorMap* tm, const void* ptr, uint64_t cols, uint64_t rows,
                    uint32_t box_c, uint32_t box_r) {
  cuuint64_t dims[2] = {cols, rows};
  cuuint64_t strides[1] = {cols * 2};
  cuuint32_t box[2] = {box_c, box_r};
  cuuint32_t es[2] = {1, 1};
  enc(tm, CU_TENSOR_MAP_DATA_TYPE_BFLOAT16, 2, const_cast<void*>(ptr), dims, strides, box, es,
      CU_TENSOR_MAP_INTERLEAVE_NONE, CU_TENSOR_MAP_SWIZZLE_128B, CU_TENSOR_MAP_L2_PROMOTION_L2_256B,
      CU_TENSOR_MAP_FLOAT_OOB_FILL_NONE);
}

extern "C" void kernel_launch(void* const* d_in, const int* in_sizes, int n_in, void* d_out, int out_size) {
  const bf16* x = (const bf16*)d_in[0];
  const bf16* kc = (const bf16*)d_in[1];
  const bf16* vc = (const bf16*)d_in[2];
  const bf16* wq = (const bf16*)d_in[3];
  const bf16* wo = (const bf16*)d_in[4];
  const bf16* w1 = (const bf16*)d_in[6];
  const bf16* b1 = (const bf16*)d_in[7];
  const bf16* w2 = (const bf16*)d_in[8];
  const bf16* b2 = (const bf16*)d_in[9];
  bf16* out = (bf16*)d_out;

  CUtensorMap tm_xn, tm_y, tm_wq, tm_w1, tm_k, tm_v, tm_ost, tm_hst, tm_old, tm_hld, tm_wo, tm_w2;
  {
    void* fn = nullptr;
    cudaDriverEntryPointQueryResult qres;
    cudaGetDriverEntryPoint("cuTensorMapEncodeTiled", &fn, cudaEnableDefault, &qres);
    PFN_encodeTiled enc = (PFN_encodeTiled)fn;
    void *p_xn, *p_y, *p_o, *p_h;
    cudaGetSymbolAddress(&p_xn, g_xn);
    cudaGetSymbolAddress(&p_y, g_y);
    cudaGetSymbolAddress(&p_o, g_o);
    cudaGetSymbolAddress(&p_h, g_h);
    make_tm(enc, &tm_xn, p_xn, DM, SQ, 64, 128);
    make_tm(enc, &tm_y, p_y, DM, SQ, 64, 128);
    make_tm(enc, &tm_wq, wq, HD, DM, 64, 64);
    make_tm(enc, &tm_w1, w1, FF, DM, 64, 64);
    make_tm(enc, &tm_k, kc, DH, (uint64_t)NH * SQ, 64, 128);
    make_tm(enc, &tm_v, vc, DH, (uint64_t)NH * SQ, 64, 128);
    make_tm(enc, &tm_ost, p_o, HD, SQ, 64, 64);
    make_tm(enc, &tm_hst, p_h, FF, SQ, 64, 64);
    make_tm(enc, &tm_old, p_o, HD, SQ, 64, 128);
    make_tm(enc, &tm_hld, p_h, FF, SQ, 64, 128);
    make_tm(enc, &tm_wo, wo, DM, HD, 64, 64);
    make_tm(enc, &tm_w2, w2, DM, FF, 64, 64);
    cudaFuncSetAttribute(attn_kernel, cudaFuncAttributeMaxDynamicSharedMemorySize, ATT_SMEM);
    cudaFuncSetAttribute(final_kernel, cudaFuncAttributeMaxDynamicSharedMemorySize, F_SMEM);
  }
  cudaLaunchAttribute at[1];
  at[0].id = cudaLaunchAttributeProgrammaticStreamSerialization;
  at[0].val.programmaticStreamSerializationAllowed = 1;
  cudaLaunchConfig_t cfg = {};
  cfg.stream = cudaStreamPerThread; cfg.attrs = at; cfg.numAttrs = 1;
  cfg.gridDim = dim3(SQ / 8); cfg.blockDim = dim3(256); cfg.dynamicSmemBytes = 0;
  cudaLaunchKernelEx(&cfg, ln_kernel, x);
  cfg.gridDim = dim3(ATT_CTAS + MLP1_CTAS); cfg.blockDim = dim3(384); cfg.dynamicSmemBytes = ATT_SMEM;
  cudaLaunchKernelEx(&cfg, attn_kernel, tm_xn, tm_y, tm_wq, tm_w1, tm_k, tm_v, tm_ost, tm_hst, b1);
  cfg.gridDim = dim3(128); cfg.dynamicSmemBytes = F_SMEM;
  cudaLaunchKernelEx(&cfg, final_kernel, tm_old, tm_wo, tm_hld, tm_w2, x, b2, out);
}
```
